```python
import torch

def _softmax(x, axis=-1):
    return torch.softmax(x, dim=axis)
def _gelu(x):
    return torch.nn.functional.gelu(x, approximate="tanh")
def _silu(x):
    return torch.nn.functional.silu(x)
def _sigmoid(x):
    return torch.sigmoid(x)
def _layernorm(x, axis=-1, eps=1e-5):
    m = x.mean(dim=axis, keepdim=True)
    v = x.var(dim=axis, keepdim=True, unbiased=False)
    return (x - m) / torch.sqrt(v + eps)
def _scatter_add(tgt, idx, src, axis=0):
    return tgt.clone().index_add_(axis, idx, src)
def _segment_sum(src, seg, n):
    out = torch.zeros((n,) + src.shape[1:], dtype=src.dtype)
    return out.index_add_(0, seg, src)
def _pad(x, pw):
    flat = tuple(v for pair in reversed(pw) for v in pair)
    return torch.nn.functional.pad(x, flat)

kernel_name = 'standalone__gqa_block_cached__near_ridge'

def setup_inputs():

    _w = (lambda a: (lambda t: t.to(torch.bfloat16) if t.is_floating_point() else t)(torch.as_tensor(a)))
    B, Sq, D = 32, 96, 640
    Hq, Hkv, Sk, Dh = 32, 32, 512, 128
    assert Hq % Hkv == 0, (Hq, Hkv)
    return {
        "x": _w((lambda *s: torch.randn(*s, dtype=torch.bfloat16) * 0.8)(B, Sq, D)),
        "k_cache": _w((lambda *s: torch.randn(*s, dtype=torch.bfloat16) * 0.8)(B, Hkv, Sk, Dh)),
        "v_cache": _w((lambda *s: torch.randn(*s, dtype=torch.bfloat16) * 0.05)(B, Hkv, Sk, Dh)),
        "wq": _w((lambda *s: torch.randn(*s, dtype=torch.bfloat16) * 0.8)(D, Hq * Dh) * (D ** -0.5)),
        "wo": _w((lambda *s: torch.randn(*s, dtype=torch.bfloat16) * 0.05)(Hq * Dh, D) * ((Hq * Dh) ** -0.5)),
    }

def reference(x, k_cache, v_cache, wq, wo):
    B, Sq, D = x.shape
    Hq, Dh = 32, 128
    Hkv = k_cache.shape[1]
    rep = Hq // Hkv
    q = (lambda x, *d: x.permute(*d))((x @ wq).reshape(B, Sq, Hq, Dh), 0, 2, 1, 3)
    k = (lambda x, n, axis: torch.repeat_interleave(x, n, dim=axis))(k_cache, rep, axis=1)
    v = (lambda x, n, axis: torch.repeat_interleave(x, n, dim=axis))(v_cache, rep, axis=1)
    scores = torch.einsum("bhqd,bhkd->bhqk", q, k) * (Dh ** -0.5)
    p = _softmax(scores, axis=-1)
    o = torch.einsum("bhqk,bhkd->bhqd", p, v)
    return (lambda x, *d: x.permute(*d))(o, 0, 2, 1, 3).reshape(B, Sq, Hq * Dh) @ wo
```

```cpp
#include <cuda_runtime.h>
#include <cuda.h>
#include <cuda_bf16.h>
#include <stdint.h>

namespace {

constexpr int NB = 32, SQ = 96, DM = 640, NH = 32, SK = 512, DH = 128;
constexpr int NROUND = 8;
constexpr int NCTA = 128;

#define KV_SLOTS_ 4
#define W_SLOTS_ 3
constexpr int KV_SLOTS = KV_SLOTS_;
constexpr int KV_BYTES = 16384;
constexpr int W_SLOTS = W_SLOTS_;
constexpr int W_BYTES = 36864;
constexpr int W_BOFF = 24576;
constexpr int W_XA = 8192, W_XB = 20480, Q_STAGES = 8;
constexpr int TILE_B = 12288;

constexpr int OFF_KV = 0;
constexpr int OFF_W = OFF_KV + KV_SLOTS * KV_BYTES;
constexpr int OFF_Q = OFF_W + W_SLOTS * W_BYTES;
constexpr int OFF_P = OFF_Q + 2 * TILE_B;
constexpr int OFF_MISC = OFF_P + 2 * TILE_B;
constexpr int OFF_BAR = OFF_MISC;
constexpr int OFF_WRED = OFF_BAR + 256;
constexpr int OFF_NEGM = OFF_WRED + 1536;
constexpr int OFF_DELTA = OFF_NEGM + 768;
constexpr int OFF_ALPHA = OFF_DELTA + 384;
constexpr int OFF_LINV = OFF_ALPHA + 384;
constexpr int OFF_LRED = OFF_LINV + 384;
constexpr int OFF_CNT = OFF_LRED + 1536;
constexpr int SMEM_USED = OFF_CNT + 16;
constexpr int SMEM_BYTES = SMEM_USED + 1024;

constexpr int BAR_KVFULL = 0;
constexpr int BAR_KVEMPTY = BAR_KVFULL + 8;
constexpr int BAR_WFULL = 16;
constexpr int BAR_WEMPTY = 20;
constexpr int BAR_QFULL = 24;
constexpr int BAR_QEMPTY = 25;
constexpr int BAR_OFULL = 26;
constexpr int BAR_OFREE = 27;
constexpr int BAR_OLOCAL = 30;
constexpr int BAR_OREM = 5;
constexpr int BAR_TOK = 29;
constexpr int BAR_OK = 28;

static_assert(KV_SLOTS == 4, "barrier map and tail buffers assume 4 KV slots");
__host__ __device__ constexpr int off_orem(int i) { return i < 2 ? OFF_KV + i * 2 * TILE_B : OFF_P; }

constexpr float QSCALE = 0.12751743459f;
constexpr int S_HI_BITS = 0x41C00000;
#define KV_PACE 600
#define Q_FLOAT 1
#define TAIL_AFTER_READ 1
#define V_EARLY 0
#define P_CHAIN 2
#define P_DEPTH_O 2
#define P_DEPTH_Q 1
#define PV_SPLIT 2
#define PV_AT0 1
#define PV_AT1 2
#define KV_POLL 40
#define KV_GUARD 2
#define KV_PFMAX 6

__device__ __align__(1024) uint8_t g_oscratch[(size_t)NB * 2 * 4 * 2 * TILE_B];
constexpr int MBOX = 288;
__device__ __align__(128) unsigned int g_flags[NCTA * MBOX];
__device__ unsigned int g_epoch;
__device__ unsigned int g_done;

#define O_ROT 0
#define POLL_NS 100
#define PUB_RELAXED 0
#define GATES_Q 0
#define GATES_OQ 0
#define GATES_O5 0
#define GATES_O6 0
#define KV_LATE 100000
#define KV_LATEMAX 1
#define KV_SCHED 735
#define KV_DELAY 1000
#define PSTEP 5
#define PROUND 4
#define TW_BEGIN() do {} while (0)
#define TW_END(acc) do {} while (0)
#define TW_DUMP(idx, acc) do {} while (0)
#define PROF(idx) do {} while (0)
#define PROFG(idx) do {} while (0)

__device__ __forceinline__ uint32_t smem_u32(const void* p) { return (uint32_t)__cvta_generic_to_shared(p); }
__device__ __forceinline__ uint32_t globaltimer_lo() { uint32_t t; asm volatile("mov.u32 %0, %%globaltimer_lo;" : "=r"(t)); return t; }
__device__ __forceinline__ bool elect_one() {
  uint32_t p;
  asm volatile("{ .reg .pred P; elect.sync _|P, 0xffffffff; selp.u32 %0, 1, 0, P; }" : "=r"(p));
  return p != 0;
}
__device__ __forceinline__ void mbar_init(uint32_t bar, uint32_t cnt) {
  asm volatile("mbarrier.init.shared::cta.b64 [%0], %1;" :: "r"(bar), "r"(cnt) : "memory");
}
__device__ __forceinline__ void mbar_expect_tx(uint32_t bar, uint32_t bytes) {
  asm volatile("mbarrier.arrive.expect_tx.shared::cta.b64 _, [%0], %1;" :: "r"(bar), "r"(bytes) : "memory");
}
__device__ __forceinline__ void mbar_arrive(uint32_t bar) {
  asm volatile("mbarrier.arrive.shared::cta.b64 _, [%0];" :: "r"(bar) : "memory");
}
__device__ __forceinline__ void l2_prefetch(const void* p, uint32_t bytes) {
  asm volatile("cp.async.bulk.prefetch.L2.global [%0], %1;" :: "l"(p), "r"(bytes) : "memory");
}
__device__ __forceinline__ void mbar_arrive_cluster_if(uint32_t cbar, bool on) {
  asm volatile("{ .reg .pred p; setp.ne.u32 p, %1, 0; @p mbarrier.arrive.release.cta.shared::cluster.b64 _, [%0]; }"
               :: "r"(cbar), "r"((uint32_t)on) : "memory");
}
__device__ __forceinline__ uint32_t mapa(uint32_t addr, uint32_t cta) {
  uint32_t r; asm("mapa.shared::cluster.u32 %0, %1, %2;" : "=r"(r) : "r"(addr), "r"(cta)); return r;
}
__device__ __forceinline__ bool mbar_test(uint32_t bar, uint32_t parity) {
  uint32_t ok;
  asm volatile("{ .reg .pred P; mbarrier.test_wait.parity.shared::cta.b64 P, [%1], %2; selp.u32 %0, 1, 0, P; }"
               : "=r"(ok) : "r"(bar), "r"(parity) : "memory");
  return ok != 0;
}
__device__ __forceinline__ void tok_post(uint32_t bar, uint32_t word, uint32_t n, bool on) {
  asm volatile("{ .reg .pred p; setp.ne.u32 p, %2, 0; @p st.volatile.shared.u32 [%0], %1; }" :: "r"(word), "r"(n), "r"((uint32_t)on) : "memory");
}
__device__ __forceinline__ bool wait_ok_or_tag(uint32_t bar, uint32_t parity, uint32_t word, uint32_t tag) {
  uint32_t r;
  asm volatile(
      "{\n"
      ".reg .pred P;\n"
      ".reg .u32 c, v;\n"
      "mov.u32 %0, 0;\n"
      "mbarrier.test_wait.parity.shared::cta.b64 P, [%1], %2;\n"
      "@P bra DONE;\n"
      "mov.u32 c, 0;\n"
      "LOOP:\n"
      "ld.acquire.cta.shared.u32 v, [%3];\n"
      "setp.eq.u32 P, v, %4;\n"
      "@P mov.u32 %0, 1;\n"
      "@P bra DONE;\n"
      "mbarrier.test_wait.parity.shared::cta.b64 P, [%1], %2;\n"
      "@P bra DONE;\n"
      "add.u32 c, c, 1;\n"
      "setp.lt.u32 P, c, 0x4000000;\n"
      "@P bra LOOP;\n"
      "trap;\n"
      "DONE:\n"
      "}\n" : "=r"(r) : "r"(bar), "r"(parity), "r"(word), "r"(tag) : "memory");
  return r != 0;
}
__device__ __forceinline__ uint32_t lds_acq(uint32_t a) {
  uint32_t v; asm volatile("ld.acquire.cta.shared.u32 %0, [%1];" : "=r"(v) : "r"(a) : "memory"); return v;
}
__device__ __forceinline__ void sts_rel(uint32_t a, uint32_t v) {
  asm volatile("st.release.cta.shared.u32 [%0], %1;" :: "r"(a), "r"(v) : "memory");
}
__device__ __forceinline__ void smem_wait_ge(uint32_t a, uint32_t need) {
  uint32_t it = 0;
  while (lds_acq(a) < need) {
    if (++it > (1u << 24)) __trap();
    __nanosleep(20);
  }
}
__device__ __forceinline__ uint32_t ldg_acq(const unsigned int* p) {
  uint32_t v; asm volatile("ld.acquire.gpu.global.u32 %0, [%1];" : "=r"(v) : "l"(p) : "memory"); return v;
}
__device__ __forceinline__ void post4(unsigned int* p, uint32_t v) {
#pragma unroll
  for (int i = 0; i < 4; i++) asm volatile("st.relaxed.gpu.global.u32 [%0], %1;" :: "l"(p + i * MBOX), "r"(v) : "memory");
}
__device__ __forceinline__ void tma3d_prefetch(const CUtensorMap* m, int c0, int c1, int c2) {
  asm volatile("cp.async.bulk.prefetch.tensor.3d.L2.global [%0, {%1,%2,%3}];" :: "l"(m), "r"(c0), "r"(c1), "r"(c2) : "memory");
}
__device__ __forceinline__ void mbar_arrive_if(uint32_t bar, bool on) {
  asm volatile("{ .reg .pred p; setp.ne.u32 p, %1, 0; @p mbarrier.arrive.shared::cta.b64 _, [%0]; }" :: "r"(bar), "r"((uint32_t)on) : "memory");
}
__device__ __forceinline__ void sts_if(uint32_t a, uint32_t v, bool on) {
  asm volatile("{ .reg .pred p; setp.ne.u32 p, %2, 0; @p st.volatile.shared.u32 [%0], %1; }" :: "r"(a), "r"(v), "r"((uint32_t)on) : "memory");
}
__device__ __forceinline__ void prefetch_map(const CUtensorMap* m) {
  asm volatile("prefetch.tensormap [%0];" :: "l"(m) : "memory");
}
__device__ __forceinline__ void mbar_wait(uint32_t bar, uint32_t parity) {
  asm volatile(
      "{\n"
      ".reg .pred P;\n"
      ".reg .u32 c;\n"
      "mbarrier.try_wait.parity.shared::cta.b64 P, [%0], %1;\n"
      "@P bra DONE;\n"
      "mov.u32 c, 0;\n"
      "LOOP:\n"
      "mbarrier.try_wait.parity.shared::cta.b64 P, [%0], %1;\n"
      "@P bra DONE;\n"
      "add.u32 c, c, 1;\n"
      "setp.lt.u32 P, c, 0x400000;\n"
      "@P bra LOOP;\n"
      "trap;\n"
      "DONE:\n"
      "}\n" :: "r"(bar), "r"(parity) : "memory");
}
__device__ __forceinline__ void mbar_wait_unless(uint32_t bar, uint32_t parity, uint32_t known) {
  asm volatile(
      "{\n"
      ".reg .pred P;\n"
      ".reg .u32 c;\n"
      "setp.ne.u32 P, %2, 0;\n"
      "@P bra.uni DONE;\n"
      "mov.u32 c, 0;\n"
      "LOOP:\n"
      "mbarrier.try_wait.parity.shared::cta.b64 P, [%0], %1;\n"
      "@P bra DONE;\n"
      "add.u32 c, c, 1;\n"
      "setp.lt.u32 P, c, 0x400000;\n"
      "@P bra LOOP;\n"
      "trap;\n"
      "DONE:\n"
      "}\n" :: "r"(bar), "r"(parity), "r"(known) : "memory");
}
__device__ __forceinline__ void tma3d_hint(uint32_t dst, const CUtensorMap* m, int c0, int c1, int c2, uint32_t bar, uint64_t pol) {
  asm volatile("cp.async.bulk.tensor.3d.shared::cluster.global.mbarrier::complete_tx::bytes.L2::cache_hint [%0], [%1, {%3,%4,%5}], [%2], %6;"
               :: "r"(dst), "l"(m), "r"(bar), "r"(c0), "r"(c1), "r"(c2), "l"(pol) : "memory");
}
__device__ __forceinline__ void tma3d_mc(uint32_t dst, const CUtensorMap* m, int c0, int c1, int c2, uint32_t bar, uint16_t mask) {
  asm volatile("cp.async.bulk.tensor.3d.shared::cluster.global.mbarrier::complete_tx::bytes.multicast::cluster [%0], [%1, {%3,%4,%5}], [%2], %6;"
               :: "r"(dst), "l"(m), "r"(bar), "r"(c0), "r"(c1), "r"(c2), "h"(mask) : "memory");
}
__device__ __forceinline__ void tma5d_x(uint32_t dst, const CUtensorMap* m, int c0, int c4, uint32_t bar) {
  asm volatile("cp.async.bulk.tensor.5d.shared::cluster.global.mbarrier::complete_tx::bytes [%0], [%1, {%3,0,0,0,%4}], [%2];"
               :: "r"(dst), "l"(m), "r"(bar), "r"(c0), "r"(c4) : "memory");
}
__device__ __forceinline__ void tma2d_store(const CUtensorMap* m, int c0, int c1, uint32_t src) {
  asm volatile("cp.async.bulk.tensor.2d.global.shared::cta.bulk_group [%0, {%2,%3}], [%1];"
               :: "l"(m), "r"(src), "r"(c0), "r"(c1) : "memory");
}
__device__ __forceinline__ void bulk_load(uint32_t dst, const void* src, uint32_t bytes, uint32_t bar) {
  asm volatile("cp.async.bulk.shared::cluster.global.mbarrier::complete_tx::bytes [%0], [%1], %2, [%3];"
               :: "r"(dst), "l"(src), "r"(bytes), "r"(bar) : "memory");
}
__device__ __forceinline__ void bulk_commit() { asm volatile("cp.async.bulk.commit_group;" ::: "memory"); }
__device__ __forceinline__ void bulk_wait_read() { asm volatile("cp.async.bulk.wait_group.read 0;" ::: "memory"); }
__device__ __forceinline__ void fence_async_smem() { asm volatile("fence.proxy.async.shared::cta;" ::: "memory"); }
__device__ __forceinline__ void fence_async_global() { asm volatile("fence.proxy.async.global;" ::: "memory"); }
__device__ __forceinline__ void cluster_arrive_relaxed() { asm volatile("barrier.cluster.arrive.relaxed;" ::: "memory"); }
__device__ __forceinline__ void cluster_wait() { asm volatile("barrier.cluster.wait.acquire;" ::: "memory"); }
template <int ID> __device__ __forceinline__ void wg_bar() { asm volatile("bar.sync %0, 128;" :: "n"(ID) : "memory"); }
template <int ID> __device__ __forceinline__ bool wg_bar_or(bool p) {
  uint32_t r;
  asm volatile("{ .reg .pred P, Q; setp.ne.u32 Q, %1, 0; bar.red.or.pred P, %2, 128, Q; selp.u32 %0, 1, 0, P; }"
               : "=r"(r) : "r"((uint32_t)p), "n"(ID) : "memory");
  return r != 0;
}
__device__ __forceinline__ void wg_fence() { asm volatile("wgmma.fence.sync.aligned;" ::: "memory"); }
__device__ __forceinline__ void wg_commit() { asm volatile("wgmma.commit_group.sync.aligned;" ::: "memory"); }
template <int N> __device__ __forceinline__ void wg_wait() { asm volatile("wgmma.wait_group.sync.aligned %0;" :: "n"(N) : "memory"); }
template <int N> __device__ __forceinline__ void reg_inc() { asm volatile("setmaxnreg.inc.sync.aligned.u32 %0;" :: "n"(N)); }
template <int N> __device__ __forceinline__ void reg_dec() { asm volatile("setmaxnreg.dec.sync.aligned.u32 %0;" :: "n"(N)); }
__device__ __forceinline__ float ex2(float x) { float y; asm("ex2.approx.ftz.f32 %0, %1;" : "=f"(y) : "f"(x)); return y; }
__device__ __forceinline__ uint32_t pack_bf16(float lo, float hi) {
  uint32_t r; asm("cvt.rn.bf16x2.f32 %0, %1, %2;" : "=r"(r) : "f"(hi), "f"(lo)); return r;
}
__device__ __forceinline__ void stsm_t(uint32_t addr, uint32_t r0, uint32_t r1, uint32_t r2, uint32_t r3) {
  asm volatile("stmatrix.sync.aligned.m8n8.x4.trans.shared.b16 [%0], {%1,%2,%3,%4};"
               :: "r"(addr), "r"(r0), "r"(r1), "r"(r2), "r"(r3) : "memory");
}
__device__ __forceinline__ float4 lds128(uint32_t a) {
  float4 v; asm volatile("ld.shared.v4.f32 {%0,%1,%2,%3}, [%4];" : "=f"(v.x), "=f"(v.y), "=f"(v.z), "=f"(v.w) : "r"(a) : "memory"); return v;
}
__device__ __forceinline__ float2 lds64(uint32_t a) {
  float2 v; asm volatile("ld.shared.v2.f32 {%0,%1}, [%2];" : "=f"(v.x), "=f"(v.y) : "r"(a) : "memory"); return v;
}
__device__ __forceinline__ float lds32(uint32_t a) {
  float v; asm volatile("ld.shared.f32 %0, [%1];" : "=f"(v) : "r"(a) : "memory"); return v;
}
__device__ __forceinline__ void sts32(uint32_t a, float v) { asm volatile("st.shared.f32 [%0], %1;" :: "r"(a), "f"(v) : "memory"); }

__device__ __forceinline__ uint64_t mkdesc(uint32_t addr) {
  return (uint64_t)((addr & 0x3FFFF) >> 4) | (1ull << 16) | (64ull << 32) | (1ull << 62);
}

__device__ __forceinline__ uint64_t mkdesc_o(uint32_t addr, uint32_t lbo) {
  return (uint64_t)(((addr & 0x3FFFF) >> 4) | (lbo << 16)) | (96ull << 32) | (2ull << 62);
}
template <int TA, int TB = 0>
__device__ __forceinline__ void wgmma96(float (&d)[48], uint64_t da, uint64_t db, int scale_d) {
  asm volatile(
      "{ .reg .pred p; setp.ne.b32 p, %50, 0;\n"
      "wgmma.mma_async.sync.aligned.m64n96k16.f32.bf16.bf16 "
      "{%0,%1,%2,%3,%4,%5,%6,%7,%8,%9,%10,%11,%12,%13,%14,%15,%16,%17,%18,%19,%20,%21,%22,%23,"
      "%24,%25,%26,%27,%28,%29,%30,%31,%32,%33,%34,%35,%36,%37,%38,%39,%40,%41,%42,%43,%44,%45,%46,%47},"
      " %48, %49, p, 1, 1, %51, %52; }\n"
      : "+f"(d[0]), "+f"(d[1]), "+f"(d[2]), "+f"(d[3]), "+f"(d[4]), "+f"(d[5]), "+f"(d[6]), "+f"(d[7]),
        "+f"(d[8]), "+f"(d[9]), "+f"(d[10]), "+f"(d[11]), "+f"(d[12]), "+f"(d[13]), "+f"(d[14]), "+f"(d[15]),
        "+f"(d[16]), "+f"(d[17]), "+f"(d[18]), "+f"(d[19]), "+f"(d[20]), "+f"(d[21]), "+f"(d[22]), "+f"(d[23]),
        "+f"(d[24]), "+f"(d[25]), "+f"(d[26]), "+f"(d[27]), "+f"(d[28]), "+f"(d[29]), "+f"(d[30]), "+f"(d[31]),
        "+f"(d[32]), "+f"(d[33]), "+f"(d[34]), "+f"(d[35]), "+f"(d[36]), "+f"(d[37]), "+f"(d[38]), "+f"(d[39]),
        "+f"(d[40]), "+f"(d[41]), "+f"(d[42]), "+f"(d[43]), "+f"(d[44]), "+f"(d[45]), "+f"(d[46]), "+f"(d[47])
      : "l"(da), "l"(db), "r"(scale_d), "n"(TA), "n"(TB));
}
__device__ __forceinline__ void wgmma48(float (&d)[24], uint64_t da, uint64_t db) {
  asm volatile(
      "wgmma.mma_async.sync.aligned.m64n48k16.f32.bf16.bf16 "
      "{%0,%1,%2,%3,%4,%5,%6,%7,%8,%9,%10,%11,%12,%13,%14,%15,%16,%17,%18,%19,%20,%21,%22,%23},"
      " %24, %25, 1, 1, 1, 1, 1;\n"
      : "+f"(d[0]), "+f"(d[1]), "+f"(d[2]), "+f"(d[3]), "+f"(d[4]), "+f"(d[5]), "+f"(d[6]), "+f"(d[7]),
        "+f"(d[8]), "+f"(d[9]), "+f"(d[10]), "+f"(d[11]), "+f"(d[12]), "+f"(d[13]), "+f"(d[14]), "+f"(d[15]),
        "+f"(d[16]), "+f"(d[17]), "+f"(d[18]), "+f"(d[19]), "+f"(d[20]), "+f"(d[21]), "+f"(d[22]), "+f"(d[23])
      : "l"(da), "l"(db));
}
template <int N>
__device__ __forceinline__ void fence_regs(float (&d)[N]) {
#pragma unroll
  for (int i = 0; i < N; i++) asm volatile("" : "+f"(d[i]) :: "memory");
}

__device__ __forceinline__ uint32_t stsm_lane_off(int warp, int lane) {
  int mat = lane >> 3, i = lane & 7;
  return (uint32_t)((mat >> 1) * 1024 + i * 128 + (((2 * warp + (mat & 1)) ^ i) << 4));
}

template <bool IS_MAX>
__device__ __forceinline__ void col_reduce_store(const float (&v)[24], int warp, int lane, uint32_t wred) {
  asm volatile("" : "+r"(lane));
  float a[12], b[6], c[3];
  const bool b4 = lane & 16, b3 = lane & 8, b2 = lane & 4;
#pragma unroll
  for (int i = 0; i < 12; i++) {
    float lo = v[i], hi = v[i + 12];
    asm("" : "+f"(lo), "+f"(hi));
    float snd = b4 ? lo : hi, kp = b4 ? hi : lo;
    float o = __shfl_xor_sync(0xffffffffu, snd, 16);
    a[i] = IS_MAX ? fmaxf(kp, o) : kp + o;
  }
#pragma unroll
  for (int i = 0; i < 6; i++) {
    float snd = b3 ? a[i] : a[i + 6], kp = b3 ? a[i + 6] : a[i];
    float o = __shfl_xor_sync(0xffffffffu, snd, 8);
    b[i] = IS_MAX ? fmaxf(kp, o) : kp + o;
  }
#pragma unroll
  for (int i = 0; i < 3; i++) {
    float snd = b2 ? b[i] : b[i + 3], kp = b2 ? b[i + 3] : b[i];
    float o = __shfl_xor_sync(0xffffffffu, snd, 4);
    c[i] = IS_MAX ? fmaxf(kp, o) : kp + o;
  }
  const int v0 = (b4 ? 12 : 0) + (b3 ? 6 : 0) + (b2 ? 3 : 0);
#pragma unroll
  for (int i = 0; i < 3; i++) {
    int vi = v0 + i;
    int col = 8 * (vi >> 1) + 2 * (lane & 3) + (vi & 1);
    sts32(wred + col * 16 + warp * 4, c[i]);
  }
}

__device__ __forceinline__ void add_if(float& l, float u, uint32_t on) {
  asm("{ .reg .pred p; setp.ne.u32 p, %2, 0; @p add.f32 %0, %0, %1; }" : "+f"(l) : "f"(u), "r"(on));
}
template <bool ACC, int J0 = 0, int J1 = 6>
__device__ __forceinline__ void exp_store(const float (&S)[48], float (&l)[24], uint32_t on, uint32_t paddr) {
#pragma unroll
  for (int jj = J0; jj < J1; jj++) {
    float p[8];
#pragma unroll
    for (int i = 0; i < 8; i++) p[i] = ex2(S[8 * jj + i]);
    if (ACC) {
      add_if(l[4 * jj + 0], p[0] + p[2], on); add_if(l[4 * jj + 1], p[1] + p[3], on);
      add_if(l[4 * jj + 2], p[4] + p[6], on); add_if(l[4 * jj + 3], p[5] + p[7], on);
    } else {
      l[4 * jj + 0] = p[0] + p[2]; l[4 * jj + 1] = p[1] + p[3];
      l[4 * jj + 2] = p[4] + p[6]; l[4 * jj + 3] = p[5] + p[7];
    }
    stsm_t(paddr + jj * 2048, pack_bf16(p[0], p[1]), pack_bf16(p[2], p[3]), pack_bf16(p[4], p[5]), pack_bf16(p[6], p[7]));
  }
}
__device__ __forceinline__ bool any_above(const float (&S)[48]) {
  int m[4];
#pragma unroll
  for (int q = 0; q < 4; q++) {
    m[q] = __vimax3_s32(__float_as_int(S[12 * q]), __float_as_int(S[12 * q + 1]), __float_as_int(S[12 * q + 2]));
#pragma unroll
    for (int i = 3; i < 11; i += 2) m[q] = __vimax3_s32(m[q], __float_as_int(S[12 * q + i]), __float_as_int(S[12 * q + i + 1]));
  }
  const int a = __vimax3_s32(m[0], m[1], __float_as_int(S[11])), b = __vimax3_s32(m[2], m[3], __float_as_int(S[23]));
  return __vimax3_s32(a, b, max(__float_as_int(S[35]), __float_as_int(S[47]))) > S_HI_BITS;
}
__device__ __forceinline__ bool any_below(const float (&S)[48]) {
  unsigned m[4];
#pragma unroll
  for (int q = 0; q < 4; q++) {
    m[q] = __vimax3_u32(__float_as_uint(S[12 * q]), __float_as_uint(S[12 * q + 1]), __float_as_uint(S[12 * q + 2]));
#pragma unroll
    for (int i = 3; i < 11; i += 2) m[q] = __vimax3_u32(m[q], __float_as_uint(S[12 * q + i]), __float_as_uint(S[12 * q + i + 1]));
  }
  const unsigned a = __vimax3_u32(m[0], m[1], __float_as_uint(S[11])), b = __vimax3_u32(m[2], m[3], __float_as_uint(S[23]));
  return __vimax3_u32(a, b, max(__float_as_uint(S[35]), __float_as_uint(S[47]))) > (0x80000000u | (unsigned)S_HI_BITS);
}

struct Ring {
  uint32_t slot, phase;
  template <int N> __device__ __forceinline__ void advance() { if (++slot == N) { slot = 0; phase ^= 1; } }
};

template <int N>
__device__ __forceinline__ void store_tile_t(const float (&a)[N], float scale, uint32_t addr) {
#pragma unroll
  for (int jj = 0; jj < N / 8; jj++) {
    const float* s = &a[8 * jj];
    stsm_t(addr + jj * 2048, pack_bf16(s[0] * scale, s[1] * scale), pack_bf16(s[2] * scale, s[3] * scale),
           pack_bf16(s[4] * scale, s[5] * scale), pack_bf16(s[6] * scale, s[7] * scale));
  }
}

template <int G>
__device__ __forceinline__ void issue_qpair(float (&q0)[48], float (&q1)[48], uint64_t da, uint64_t db, int acc) {
  const uint64_t ao = (uint64_t)(((G >> 1) * 12288 + (G & 1) * 2048) >> 4);
  wgmma96<1>(q0, da + ao, db + (uint64_t)(G * 2), G ? 1 : acc);
  wgmma96<1>(q1, da + ao + 256, db + (uint64_t)(G * 2), G ? 1 : acc);
  wg_commit();
}
__device__ __forceinline__ void issue_qpair_x(float (&q0)[48], float (&q1)[48], uint32_t st) {
  const uint64_t da = mkdesc(st + W_XA);
  const uint64_t db = (uint64_t)(((st + W_XB) & 0x3FFFF) >> 4) | (1ull << 16) | (16ull << 32) | (3ull << 62);
  wgmma96<1>(q0, da, db, 1);
  wgmma96<1>(q1, da + 128, db, 1);
  wg_commit();
}
template <int I>
__device__ __forceinline__ void issue_o1(float (&accA)[48], float (&accB)[48], float (&accH)[24], uint64_t da, uint64_t dh, uint64_t db, uint64_t dbh) {
  constexpr int kk = I / 3;
  const uint64_t ao = (uint64_t)(((kk >> 1) * 12288 + (kk & 1) * 2048) >> 4);
  if (I % 3 == 0) wgmma96<1, 1>(accA, da + ao, db + (uint64_t)(kk * 192), 1);
  if (I % 3 == 1) wgmma96<1, 1>(accB, da + ao + 256, db + (uint64_t)(kk * 192), 1);
  if (I % 3 == 2) wgmma48(accH, dh + ao, dbh + (uint64_t)(kk * 192));
}
template <int G>
__device__ __forceinline__ void issue_opair(float (&accA)[48], float (&accB)[48], float (&accH)[24], uint64_t da, uint64_t dh, uint64_t db, uint64_t dbh) {
  issue_o1<2 * G>(accA, accB, accH, da, dh, db, dbh);
  issue_o1<2 * G + 1>(accA, accB, accH, da, dh, db, dbh);
  wg_commit();
}
__device__ __forceinline__ void pack_q(float (&q0)[48], float (&q1)[48]) {
  fence_regs(q0);
  fence_regs(q1);
#pragma unroll
  for (int i = 0; i < 24; i++) q0[i] = __uint_as_float(pack_bf16(q0[2 * i] * QSCALE, q0[2 * i + 1] * QSCALE));
#pragma unroll
  for (int i = 0; i < 24; i++) q0[24 + i] = __uint_as_float(pack_bf16(q1[2 * i] * QSCALE, q1[2 * i + 1] * QSCALE));
  fence_regs(q0);
}
__device__ __forceinline__ void hand_q(const float (&q0)[48], int hd, uint32_t sb, int lane, uint32_t st_off) {
  mbar_wait(sb + OFF_BAR + BAR_QEMPTY * 8, (hd & 1) ^ 1);
#pragma unroll
  for (int jj = 0; jj < 12; jj++)
    stsm_t(sb + OFF_Q + st_off + jj * 2048, __float_as_uint(q0[4 * jj]), __float_as_uint(q0[4 * jj + 1]),
           __float_as_uint(q0[4 * jj + 2]), __float_as_uint(q0[4 * jj + 3]));
  fence_async_smem();
  __syncwarp();
  mbar_arrive_if(sb + OFF_BAR + BAR_QFULL * 8, lane == 0);
}
__device__ __forceinline__ bool wait_full_or_event(uint32_t bar, uint32_t parity, uint32_t word, uint32_t n) {
  uint32_t r;
  asm volatile(
      "{\n"
      ".reg .pred P;\n"
      ".reg .u32 c, v;\n"
      "mov.u32 c, 0;\n"
      "LOOP:\n"
      "ld.volatile.shared.u32 v, [%3];\n"
      "setp.ge.u32 P, v, %4;\n"
      "selp.u32 %0, 1, 0, P;\n"
      "@P bra DONE;\n"
      "mbarrier.test_wait.parity.shared::cta.b64 P, [%1], %2;\n"
      "@P bra DONE;\n"
      "nanosleep.u32 40;\n"
      "add.u32 c, c, 1;\n"
      "setp.lt.u32 P, c, 0x1000000;\n"
      "@P bra LOOP;\n"
      "trap;\n"
      "DONE:\n"
      "}\n" : "=r"(r) : "r"(bar), "r"(parity), "r"(word), "r"(n) : "memory");
  return r != 0;
}

__device__ __forceinline__ void proj_role(uint32_t sb, const CUtensorMap* m_out, const CUtensorMap* m_out16, int b, int j, uint32_t rank, int warp, int lane) {
  float q0[48], q1[48], accA[48], accB[48];
  struct { float v[24]; } acc_h;
  float (&accH)[24] = acc_h.v;
#pragma unroll
  for (int i = 0; i < 48; i++) { accA[i] = 0.f; accB[i] = 0.f; q0[i] = 0.f; q1[i] = 0.f; }
#pragma unroll
  for (int i = 0; i < 24; i++) accH[i] = 0.f;
  const uint32_t odd = j & 1;
  const uint32_t bars = sb + OFF_BAR;
  const uint32_t wempty_c = mapa(bars + BAR_WEMPTY * 8, (lane & 1) ^ rank);
  const uint32_t st_off = stsm_lane_off(warp, lane);
  Ring w{0, 0};
  uint32_t q_pending = 0;
  uint32_t pend = 0, cur = 0;
  auto release_prev = [&]() {
    mbar_arrive_cluster_if(wempty_c + cur * 8, pend != 0 && lane < 2);
    cur = w.slot;
    w.advance<W_SLOTS>();
  };
  auto drain_unless = [&](uint32_t chained) {
    if (!chained) {
      wg_wait<0>();
      mbar_arrive_cluster_if(wempty_c + cur * 8, lane < 2);
    }
    pend = chained;
    wg_wait<1>();
  };
#pragma unroll 1
  for (int step = 0; step < NROUND + 2; step++) {
    if (step >= 3) {
#pragma unroll 1
      for (int kc = 0; kc < 8; kc++) {
        const uint32_t st = sb + OFF_W + w.slot * W_BYTES;
        const uint32_t bt = st + W_BOFF;
        if (q_pending && pend == 0 &&
            __any_sync(0xffffffffu, wait_full_or_event(bars + (BAR_WFULL + w.slot) * 8, w.phase, sb + OFF_CNT + 12, 8 * (step - 1)))) {
          hand_q(q0, step - 1, sb, lane, st_off);
          q_pending = 0;
          if (warp == 0 && lane == 0) PROF(64 + step - 1);
        }
        mbar_wait_unless(bars + (BAR_WFULL + w.slot) * 8, w.phase, pend);
        if (step == PSTEP && warp == 0 && lane == 0) PROF(124 + 2 * kc);
        const uint64_t da = mkdesc(st + odd * 4096), dh = mkdesc(st + (odd ^ 1) * 8192), db = mkdesc_o(bt, 32), dbh = mkdesc_o(bt + odd * 512, odd ? 34 : 64);
        wg_fence();
        issue_opair<0>(accA, accB, accH, da, dh, db, dbh);
        wg_wait<1>();
        release_prev();
        issue_opair<1>(accA, accB, accH, da, dh, db, dbh);
        wg_wait<P_DEPTH_O>();
        issue_opair<2>(accA, accB, accH, da, dh, db, dbh);
        wg_wait<P_DEPTH_O>();
        issue_opair<3>(accA, accB, accH, da, dh, db, dbh);
        wg_wait<P_DEPTH_O>();
        issue_opair<4>(accA, accB, accH, da, dh, db, dbh);
        bool go = kc < 7 && mbar_test(bars + (BAR_WFULL + w.slot) * 8, w.phase);
        if (q_pending) go = go && lds_acq(sb + OFF_CNT + 12) < 8 * (step - 1);
        const uint32_t chained = !__any_sync(0xffffffffu, wg_bar_or<2>(!go));
        wg_wait<P_DEPTH_O>();
        issue_opair<5>(accA, accB, accH, da, dh, db, dbh);
        drain_unless(chained);
        if (step == PSTEP && warp == 0 && lane == 0) PROF(125 + 2 * kc);
      }
      wg_wait<0>();
    }
    if (q_pending) {
      hand_q(q0, step - 1, sb, lane, st_off);
      q_pending = 0;
      if (warp == 0 && lane == 0) PROF(64 + step - 1);
    }
    if (step < NROUND) {
#pragma unroll 1
      for (int kc = 0; kc < Q_STAGES; kc++) {
        const uint32_t st = sb + OFF_W + w.slot * W_BYTES;
        mbar_wait_unless(bars + (BAR_WFULL + w.slot) * 8, w.phase, pend);
        if (step == PSTEP && warp == 0 && lane == 0) PROF(104 + 2 * kc);
        const uint64_t da = mkdesc(st), db = mkdesc(st + W_BOFF);
        wg_fence();
        issue_qpair<0>(q0, q1, da, db, kc != 0);
        wg_wait<1>();
        release_prev();
        issue_qpair<1>(q0, q1, da, db, 1);
        wg_wait<P_DEPTH_Q>();
        issue_qpair<2>(q0, q1, da, db, 1);
        wg_wait<P_DEPTH_Q>();
        issue_qpair<3>(q0, q1, da, db, 1);
        const bool go = kc < Q_STAGES - 1 && mbar_test(bars + (BAR_WFULL + w.slot) * 8, w.phase);
        const uint32_t chained = !__any_sync(0xffffffffu, wg_bar_or<2>(!go));
        wg_wait<P_DEPTH_Q>();
        issue_qpair_x(q0, q1, st);
        drain_unless(chained);
        if (step == PSTEP && warp == 0 && lane == 0) PROF(105 + 2 * kc);
      }
      wg_wait<0>();
      pack_q(q0, q1);
      q_pending = 1;
    }
  }
#pragma unroll 1
  for (int kc = 0; kc < 8; kc++) {
    const uint32_t st = sb + OFF_W + w.slot * W_BYTES;
    const int q = kc >> 1;
    const uint32_t bt = sb + (q == 0 ? OFF_Q : q == 1 ? off_orem(0) : q == 2 ? off_orem(1) : off_orem(2)) + (kc & 1) * TILE_B;
    mbar_wait(bars + (q == 0 ? BAR_OLOCAL : BAR_OREM + q - 1) * 8, 0);
    mbar_wait(bars + (BAR_WFULL + w.slot) * 8, w.phase);
    if (NROUND + 2 == PSTEP && warp == 0 && lane == 0) PROF(124 + 2 * kc);
    const uint64_t da = mkdesc(st + odd * 4096), dh = mkdesc(st + (odd ^ 1) * 8192), db = mkdesc_o(bt, 32), dbh = mkdesc_o(bt + odd * 512, odd ? 34 : 64);
    wg_fence();
    issue_opair<0>(accA, accB, accH, da, dh, db, dbh);
    issue_opair<1>(accA, accB, accH, da, dh, db, dbh);
    wg_wait<2>();
    release_prev();
    issue_o1<4>(accA, accB, accH, da, dh, db, dbh); issue_o1<5>(accA, accB, accH, da, dh, db, dbh);
    issue_o1<6>(accA, accB, accH, da, dh, db, dbh); issue_o1<7>(accA, accB, accH, da, dh, db, dbh);
    issue_o1<8>(accA, accB, accH, da, dh, db, dbh); issue_o1<9>(accA, accB, accH, da, dh, db, dbh);
    issue_o1<10>(accA, accB, accH, da, dh, db, dbh); issue_o1<11>(accA, accB, accH, da, dh, db, dbh);
    wg_commit();
    drain_unless(kc != 1);
    if (NROUND + 2 == PSTEP && warp == 0 && lane == 0) PROF(125 + 2 * kc);
  }
  wg_wait<0>();
  if (warp == 0 && lane == 0) PROF(80);
  cluster_arrive_relaxed();
  fence_regs(accA);
  fence_regs(accB);
  fence_regs(accH);
  const int col0 = (j >> 1) * 320 + odd * 192, colh = (j >> 1) * 320 + 128;
  const uint32_t ta = sb + OFF_Q, th = sb + OFF_KV + 3 * KV_BYTES;
  store_tile_t(accA, 1.f, ta + st_off);
  store_tile_t(accB, 1.f, ta + TILE_B + st_off);
  store_tile_t(accH, 1.f, th + st_off);
  fence_async_smem();
  wg_bar<2>();
  if (warp == 0 && elect_one()) {
    tma2d_store(m_out, col0, b * SQ, ta);
    tma2d_store(m_out, col0 + 64, b * SQ, ta + TILE_B);
    tma2d_store(m_out16, colh, b * SQ + odd * 32, th);
    tma2d_store(m_out16, colh, b * SQ + odd * 32 + 16, th + 2048);
    tma2d_store(m_out16, colh, b * SQ + 64 + odd * 16, th + 4096);
    bulk_commit();
    bulk_wait_read();
  }
  __syncwarp();
  if (warp == 0 && lane == 0) { PROF(81); PROFG(255); }
  cluster_wait();
}

template <bool FIRST>
__device__ __forceinline__ void max_update(float (&S)[48], float (&O0)[48], float (&O1)[48], float (&l)[24],
                                           bool shifted, uint32_t sb, int warp, int lane) {
  asm volatile("" : "+r"(lane));
  {
    float cm[24];
#pragma unroll
    for (int jb = 0; jb < 12; jb++) {
      cm[2 * jb] = fmaxf(S[4 * jb], S[4 * jb + 2]);
      cm[2 * jb + 1] = fmaxf(S[4 * jb + 1], S[4 * jb + 3]);
    }
    col_reduce_store<true>(cm, warp, lane, sb + OFF_WRED);
  }
  wg_bar<1>();
  const int t = warp * 32 + lane;
  if (t < SQ) {
    float4 v = lds128(sb + OFF_WRED + t * 16);
    float d = fmaxf(fmaxf(v.x, v.y), fmaxf(v.z, v.w));
    const uint32_t na = sb + OFF_NEGM + (t >> 1) * 16 + (t & 1) * 4;
    float nm;
    if (FIRST) {
      nm = -d;
    } else {
      d = fmaxf(d, 0.f);
      nm = (shifted ? lds32(na) : 0.f) - d;
      sts32(sb + OFF_ALPHA + t * 4, ex2(-d));
    }
    sts32(na, nm);
    sts32(na + 8, nm);
    sts32(sb + OFF_DELTA + t * 4, d);
  }
  wg_bar<1>();
  const uint32_t co = (lane & 3) * 8;
#pragma unroll
  for (int jb = 0; jb < 12; jb++) {
    float2 d = lds64(sb + OFF_DELTA + jb * 32 + co);
    S[4 * jb] -= d.x; S[4 * jb + 1] -= d.y; S[4 * jb + 2] -= d.x; S[4 * jb + 3] -= d.y;
    if (!FIRST) {
      float2 a = lds64(sb + OFF_ALPHA + jb * 32 + co);
      l[2 * jb] *= a.x; l[2 * jb + 1] *= a.y;
      O0[4 * jb] *= a.x; O0[4 * jb + 1] *= a.y; O0[4 * jb + 2] *= a.x; O0[4 * jb + 3] *= a.y;
      O1[4 * jb] *= a.x; O1[4 * jb + 1] *= a.y; O1[4 * jb + 2] *= a.x; O1[4 * jb + 3] *= a.y;
    }
  }
}

__device__ __forceinline__ void issue_qk(float (&S)[48], uint32_t kaddr, uint32_t qaddr, int first_scale) {
  const uint64_t da = mkdesc(kaddr), db = mkdesc(qaddr);
#pragma unroll
  for (int kk = 0; kk < 8; kk++)
    wgmma96<0>(S, da + (uint64_t)(((kk >> 2) * 8192 + (kk & 3) * 32) >> 4), db + (uint64_t)(((kk >> 2) * TILE_B + (kk & 3) * 32) >> 4),
               kk == 0 ? first_scale : 1);
}
template <int K0 = 0, int K1 = 4>
__device__ __forceinline__ void issue_pv(float (&O0)[48], float (&O1)[48], uint32_t vaddr, uint32_t paddr, int first_scale) {
  const uint64_t da = mkdesc(vaddr), db = mkdesc(paddr);
#pragma unroll
  for (int kk = K0; kk < K1; kk++) {
    wgmma96<1>(O0, da + (uint64_t)((kk * 2048) >> 4), db + (uint64_t)(kk * 2), kk == 0 ? first_scale : 1);
    wgmma96<1>(O1, da + (uint64_t)((8192 + kk * 2048) >> 4), db + (uint64_t)(kk * 2), kk == 0 ? first_scale : 1);
  }
}

__device__ __forceinline__ void adv2(Ring& r) { r.slot += 2; if (r.slot >= KV_SLOTS) { r.slot -= KV_SLOTS; r.phase ^= 1; } }

__device__ __forceinline__ void make_linv(uint32_t sb, int t) {
  asm volatile("" : "+r"(t));
  if (t < SQ) {
    float4 v = lds128(sb + OFF_LRED + t * 16);
    sts32(sb + OFF_LINV + (t >> 4) * 64 + ((t >> 1) & 3) * 16 + ((t >> 3) & 1) * 8 + (t & 1) * 4,
          __fdividef(1.f, (v.x + v.y) + (v.z + v.w)));
  }
}
__device__ __forceinline__ void load_linv(float4 (&a)[6], uint32_t sb, int lane) {
  asm volatile("" : "+r"(lane));
#pragma unroll
  for (int jj = 0; jj < 6; jj++) a[jj] = lds128(sb + OFF_LINV + (lane & 3) * 16 + jj * 64);
}
template <bool LOCAL>
__device__ __forceinline__ void write_o(const float (&O0)[48], const float (&O1)[48], const float4 (&a)[6], uint8_t* dst, uint32_t sb, int warp, int lane) {
  asm volatile("" : "+r"(lane));
  const uint32_t off = warp * 3072 + (lane >> 2) * 64 + (((lane & 3) ^ (lane >> 3)) * 16);
#pragma unroll
  for (int m = 0; m < 2; m++) {
#pragma unroll
    for (int q = 0; q < 3; q++) {
#pragma unroll
      for (int h = 0; h < 2; h++) {
        const float* s = (m ? O1 : O0) + 16 * q + 2 * h;
        const uint32_t r0 = pack_bf16(s[0] * a[2 * q].x, s[1] * a[2 * q].y), r1 = pack_bf16(s[4] * a[2 * q].z, s[5] * a[2 * q].w);
        const uint32_t r2 = pack_bf16(s[8] * a[2 * q + 1].x, s[9] * a[2 * q + 1].y), r3 = pack_bf16(s[12] * a[2 * q + 1].z, s[13] * a[2 * q + 1].w);
        const uint32_t o = off + m * TILE_B + h * 1536 + q * 512;
        asm volatile("st.global.v4.b32 [%0], {%1,%2,%3,%4};" :: "l"(dst + o), "r"(r0), "r"(r1), "r"(r2), "r"(r3) : "memory");
        if (LOCAL) asm volatile("st.shared.v4.b32 [%0], {%1,%2,%3,%4};" :: "r"(sb + OFF_Q + o), "r"(r0), "r"(r1), "r"(r2), "r"(r3) : "memory");
      }
    }
  }
  __syncwarp();
  mbar_arrive_if(sb + OFF_BAR + BAR_OFULL * 8, lane == 0);
  if (LOCAL) {
    fence_async_smem();
    __syncwarp();
    mbar_arrive_if(sb + OFF_BAR + BAR_OLOCAL * 8, lane == 0);
  }
}
__device__ __forceinline__ void load_shift(float (&S)[48], uint32_t sb, int lane) {
  asm volatile("" : "+r"(lane));
  const uint32_t negm_a = sb + OFF_NEGM + (lane & 3) * 16;
#pragma unroll
  for (int jb = 0; jb < 12; jb++) {
    float4 v = lds128(negm_a + jb * 64);
    S[4 * jb] = v.x; S[4 * jb + 1] = v.y; S[4 * jb + 2] = v.z; S[4 * jb + 3] = v.w;
  }
}

__device__ __forceinline__ void attn_role(uint32_t sb, uint8_t* oslot, int warp, int lane) {
  float S[48], O0[48], O1[48];
  struct { float v[24]; int pad; } l_;
  float (&l)[24] = l_.v;
  asm volatile("" : "+r"(lane));
  const bool t0 = warp == 0 && lane == 0;
#pragma unroll
  for (int i = 0; i < 48; i++) { S[i] = 0.f; O0[i] = 0.f; O1[i] = 0.f; }
  const uint32_t bars = sb + OFF_BAR;
  const uint32_t st_off = stsm_lane_off(warp, lane);
  Ring kr{0, 0}, vr{2 % KV_SLOTS, 0};
  uint32_t okp = 0;
  mbar_wait(bars + BAR_QFULL * 8, 0);
  mbar_wait(bars + BAR_KVFULL * 8, 0);
  if (warp == 0 && lane == 0) { PROF(0); PROFG(240); }
  wg_fence();
  issue_qk(S, sb + OFF_KV, sb + OFF_Q, 0);
  wg_commit();
  tok_post(bars + BAR_TOK * 8, sb + OFF_CNT + 12, 1, t0);
  wg_wait<0>();
  fence_regs(S);
  mbar_arrive_if(bars + BAR_KVEMPTY * 8, lane == 0);
  kr.slot = 1;
  exp_store<false>(S, l, 1, sb + OFF_P + st_off);
  uint32_t shifted = __any_sync(0xffffffffu, wg_bar_or<1>(any_above(S) || any_below(S)));
#pragma unroll 1
  for (int r = 0; r < NROUND; r++) {
    if (shifted) {
      max_update<true>(S, O0, O1, l, false, sb, warp, lane);
      exp_store<false>(S, l, 1, sb + OFF_P + st_off);
      load_shift(S, sb, lane);
    }
    { TW_BEGIN(); mbar_wait(bars + (BAR_KVFULL + kr.slot) * 8, kr.phase); TW_END(twk); }
    wg_fence();
    issue_qk(S, sb + OFF_KV + kr.slot * KV_BYTES, sb + OFF_Q, shifted);
    wg_commit();
    if (r > 0) {
      { TW_BEGIN(); mbar_wait(bars + BAR_OFREE * 8, (r - 1) & 1); TW_END(two); }
      float4 a[6];
      load_linv(a, sb, lane);
      write_o<false>(O0, O1, a, oslot + ((r - 1) & 1) * (8 * TILE_B), sb, warp, lane);
      if (warp == 0 && lane == 0) PROF(r * 4 - 1);
    }
    if (warp == 0 && lane == 0) PROF(r * 4 + 1);
    uint32_t k_rdy = 0, v_rdy = 0;
    int c = 1;
#pragma unroll 1
    while (true) {
      fence_async_smem();
      wg_bar<1>();
      { TW_BEGIN(); mbar_wait_unless(bars + (BAR_KVFULL + vr.slot) * 8, vr.phase, v_rdy); TW_END(twv); }
      const uint32_t va = sb + OFF_KV + vr.slot * KV_BYTES, pb = sb + OFF_P + ((c - 1) & 1) * TILE_B;
      wg_fence();
      issue_pv<0, PV_SPLIT>(O0, O1, va, pb, c > 1);
      wg_commit();
      tok_post(bars + BAR_TOK * 8, sb + OFF_CNT + 12, r * 8 + c + 1, t0);
      wg_wait<1>();
      fence_regs(S);
      if (r == PROUND && warp == 0 && lane == 0) PROF(200 + c);
      mbar_arrive_if(bars + (BAR_KVEMPTY + kr.slot) * 8, lane == 0);
      mbar_arrive_if(bars + BAR_QEMPTY * 8, lane == 0 && c == 7);
      adv2(kr);
      const uint32_t in_range = !__any_sync(0xffffffffu, any_above(S));
      const uint32_t tag = r * 8 + c;
      mbar_arrive_if(bars + BAR_OK * 8, lane == 0 && in_range);
      sts_if(sb + OFF_CNT + 8, tag, !in_range);
      const uint32_t pa = sb + OFF_P + (c & 1) * TILE_B + st_off;
      const uint32_t vempty = bars + (BAR_KVEMPTY + vr.slot) * 8;
      adv2(vr);
      if (PV_SPLIT == 4) {
        exp_store<true, 0, 4>(S, l, in_range, pa);
      } else {
        exp_store<true, 0, PV_AT0>(S, l, in_range, pa);
        wg_fence();
        issue_pv<2, 3>(O0, O1, va, pb, 1);
        wg_commit();
        exp_store<true, PV_AT0, PV_AT1>(S, l, in_range, pa);
        wg_fence();
        issue_pv<3, 4>(O0, O1, va, pb, 1);
        wg_commit();
        exp_store<true, PV_AT1, 4>(S, l, in_range, pa);
      }
      const uint32_t seen = __ballot_sync(0xffffffffu,
          mbar_test(bars + (lane == 0 ? BAR_KVFULL + kr.slot : lane == 1 ? BAR_KVFULL + vr.slot : BAR_OK) * 8,
                    lane == 0 ? kr.phase : lane == 1 ? vr.phase : okp) && (lane < 2 || !shifted));
      k_rdy = seen & 1;
      v_rdy = seen & 2;
      const bool careful = !(seen & 4);
      if (V_EARLY) {
        wg_wait<0>();
        mbar_arrive_if(vempty, lane == 0);
      }
      exp_store<true, 4, 6>(S, l, in_range, pa);
      wg_wait<0>();
      fence_regs(O0);
      fence_regs(O1);
      if (!V_EARLY) mbar_arrive_if(vempty, lane == 0);
      okp ^= 1;
      if (r == PROUND && warp == 0 && lane == 0) { PROF(210 + c); PROF(220 + c); }
      c++;
      if (__builtin_expect(careful, 0)) {
        if (__any_sync(0xffffffffu, wait_ok_or_tag(bars + BAR_OK * 8, okp ^ 1, sb + OFF_CNT + 8, tag))) {
          wg_bar<1>();
          mbar_arrive_if(bars + BAR_OK * 8, lane == 0 && !in_range);
          max_update<false>(S, O0, O1, l, shifted, sb, warp, lane);
          shifted = 1;
          exp_store<true>(S, l, !in_range, pa);
        }
        if (shifted) load_shift(S, sb, lane);
      }
      if (c == 8) break;
      { TW_BEGIN(); mbar_wait_unless(bars + (BAR_KVFULL + kr.slot) * 8, kr.phase, k_rdy); TW_END(twk); }
      if (r == PROUND && warp == 0 && lane == 0) PROF(190 + c);
      wg_fence();
      issue_qk(S, sb + OFF_KV + kr.slot * KV_BYTES, sb + OFF_Q, shifted);
      wg_commit();
    }
    if (r + 1 < NROUND) {
      { TW_BEGIN(); mbar_wait(bars + BAR_QFULL * 8, (r + 1) & 1); TW_END(twq); }
      { TW_BEGIN(); mbar_wait_unless(bars + (BAR_KVFULL + kr.slot) * 8, kr.phase, k_rdy); TW_END(twk); }
      if (warp == 0 && lane == 0) { PROF(r * 4 + 4); PROFG(241 + r); }
      wg_fence();
      issue_qk(S, sb + OFF_KV + kr.slot * KV_BYTES, sb + OFF_Q, 0);
      wg_commit();
      col_reduce_store<false>(l, warp, lane, sb + OFF_LRED);
      fence_async_smem();
      wg_bar<1>();
      { TW_BEGIN(); mbar_wait_unless(bars + (BAR_KVFULL + vr.slot) * 8, vr.phase, v_rdy); TW_END(twv); }
      if (warp == 0 && lane == 0) { PROF(r * 4 + 2); TW_DUMP(32 + r, twk); TW_DUMP(40 + r, twv); TW_DUMP(48 + r, twq); TW_DUMP(56 + r, two); }
      wg_fence();
      issue_pv(O0, O1, sb + OFF_KV + vr.slot * KV_BYTES, sb + OFF_P + TILE_B, 1);
      wg_commit();
      tok_post(bars + BAR_TOK * 8, sb + OFF_CNT + 12, r * 8 + 9, t0);
      wg_wait<1>();
      fence_regs(S);
      mbar_arrive_if(bars + (BAR_KVEMPTY + kr.slot) * 8, lane == 0);
      adv2(kr);
      make_linv(sb, warp * 32 + lane);
      exp_store<false>(S, l, 1, sb + OFF_P + st_off);
      const bool bad = any_above(S) || any_below(S);
      wg_wait<0>();
      fence_regs(O0);
      fence_regs(O1);
      mbar_arrive_if(bars + (BAR_KVEMPTY + vr.slot) * 8, lane == 0);
      adv2(vr);
      shifted = __any_sync(0xffffffffu, wg_bar_or<1>(bad));
    }
  }
  vr = kr;
  col_reduce_store<false>(l, warp, lane, sb + OFF_LRED);
  fence_async_smem();
  wg_bar<1>();
  { TW_BEGIN(); mbar_wait(bars + (BAR_KVFULL + vr.slot) * 8, vr.phase); TW_END(twv); }
  if (warp == 0 && lane == 0) { PROF(30); TW_DUMP(39, twk); TW_DUMP(47, twv); }
  wg_fence();
  issue_pv(O0, O1, sb + OFF_KV + vr.slot * KV_BYTES, sb + OFF_P + TILE_B, 1);
  wg_commit();
  make_linv(sb, warp * 32 + lane);
  mbar_wait(bars + BAR_OFREE * 8, (NROUND - 1) & 1);
  wg_bar<1>();
  float4 a[6];
  load_linv(a, sb, lane);
  wg_wait<0>();
  fence_regs(O0);
  fence_regs(O1);
  write_o<true>(O0, O1, a, oslot + ((NROUND - 1) & 1) * (8 * TILE_B), sb, warp, lane);
  if (warp == 0 && lane == 0) PROF(31);
  cluster_arrive_relaxed();
  cluster_wait();
}

__global__ void __cluster_dims__(2, 1, 1) __launch_bounds__(384, 1)
gqa_block_kernel(const __grid_constant__ CUtensorMap m_k, const __grid_constant__ CUtensorMap m_v,
                 const __grid_constant__ CUtensorMap m_wq, const __grid_constant__ CUtensorMap m_wo,
                 const __grid_constant__ CUtensorMap m_x, const __grid_constant__ CUtensorMap m_out,
                 const __grid_constant__ CUtensorMap m_wq2, const __grid_constant__ CUtensorMap m_x2,
                 const __grid_constant__ CUtensorMap m_out16,
                 const uint8_t* __restrict__ p_x, const uint8_t* __restrict__ p_wo,
                 const uint8_t* __restrict__ p_k, const uint8_t* __restrict__ p_v) {
  extern __shared__ uint8_t smem_raw[];
  const uint32_t sb = (smem_u32(smem_raw) + 1023u) & ~1023u;
  const int warp_id = __shfl_sync(0xffffffffu, (int)(threadIdx.x >> 5), 0);
  const int lane = threadIdx.x & 31;
  const int wg = warp_id >> 2, warp = warp_id & 3;
  const uint32_t bars = sb + OFF_BAR;

  const int cl = blockIdx.x >> 1;
  const uint32_t rank = blockIdx.x & 1;
  int g, j;
  if (cl < 4) { g = 15; j = cl; }
  else if (cl < 36) { g = (cl - 4) & 7; j = (cl - 4) >> 3; }
  else { g = 8 + (cl - 36) % 7; j = (cl - 36) / 7; }
  const int b = 2 * g + (int)rank;

  if (warp_id < 2) {
    if (elect_one()) l2_prefetch(p_x + (size_t)(b * 4 + j) * 30720 + warp_id * 15360, 15360);
  } else if (warp_id == 2) {
    if (b < 20 && elect_one()) tma3d_prefetch(&m_wq, 0, b * 32, j * 2);
  } else if (warp_id == 10) {
    if (elect_one()) { prefetch_map(&m_x); prefetch_map(&m_wq); prefetch_map(&m_x2); prefetch_map(&m_wq2); prefetch_map(&m_k); prefetch_map(&m_v); }
  } else if (threadIdx.x == 256) {
    PROF(90);
    PROFG(254);
    sts32(sb + OFF_CNT, 0.f);
    sts32(sb + OFF_CNT + 4, 0.f);
    sts32(sb + OFF_CNT + 8, 0.f);
    for (int i = 0; i < KV_SLOTS; i++) { mbar_init(bars + (BAR_KVFULL + i) * 8, 1); mbar_init(bars + (BAR_KVEMPTY + i) * 8, 4); }
    for (int i = 0; i < W_SLOTS; i++) { mbar_init(bars + (BAR_WFULL + i) * 8, 1); mbar_init(bars + (BAR_WEMPTY + i) * 8, 8); }
    mbar_init(bars + BAR_QFULL * 8, 4);
    mbar_init(bars + BAR_QEMPTY * 8, 4);
    mbar_init(bars + BAR_OFULL * 8, 4);
    mbar_init(bars + BAR_OFREE * 8, 1);
    mbar_init(bars + BAR_OK * 8, 4);
    mbar_init(bars + BAR_OLOCAL * 8, 4);
    for (int i = 0; i < 3; i++) mbar_init(bars + (BAR_OREM + i) * 8, 1);
    sts32(sb + OFF_CNT + 12, 0.f);
    asm volatile("fence.mbarrier_init.release.cluster;" ::: "memory");
  }
  __syncwarp();
  cluster_arrive_relaxed();
  __syncthreads();
  cluster_wait();

  if (wg == 0) {
    reg_inc<232>();
    attn_role(sb, g_oscratch + (size_t)(b * 8 + j) * 2 * TILE_B, warp, lane);
  } else if (wg == 1) {
    reg_inc<248>();
    proj_role(sb, &m_out, &m_out16, b, j, rank, warp, lane);
  } else {
    reg_dec<24>();
    unsigned int* const flags = &g_flags[(b * 4 + j) * MBOX];
    unsigned int* const post = &g_flags[b * 4 * MBOX + j];
    if (warp == 0) {
      uint64_t pol;
      asm volatile("createpolicy.fractional.L2::evict_first.b64 %0, 1.0;" : "=l"(pol));
      auto tile_is_v = [](int n) { return (n == 16 * NROUND - 1) || (n > 0 && (n & 1) == 0); };
      auto tile_row = [&](int n) {
        const int ch = (n == 16 * NROUND - 1) ? 63 : (tile_is_v(n) ? (n >> 1) - 1 : (n + 1) >> 1);
        return (b * NH + 4 * (ch >> 3) + j) * SK + (ch & 7) * 64;
      };
      Ring kv{0, 1}, lag{KV_SLOTS - KV_GUARD, 1};
      uint32_t t_ok = globaltimer_lo() + KV_DELAY;
      uint32_t t_sched = t_ok;
      int np = 0;
#pragma unroll 1
      for (int n = 0; n < 16 * NROUND; n++) {
        uint32_t it = 0;
        while (!mbar_test(bars + (BAR_KVEMPTY + kv.slot) * 8, kv.phase)) {
          __nanosleep(KV_POLL);
          if (np < n + KV_PFMAX && np < 16 * NROUND) {
            const uint32_t now = globaltimer_lo();
            if ((int)(now - t_ok) >= 0 && (int)(now - t_sched) >= 0 &&
                (((int)(now - t_sched) >= KV_LATE && np < n + KV_LATEMAX) || mbar_test(bars + (BAR_KVFULL + lag.slot) * 8, lag.phase))) {
              if (elect_one()) l2_prefetch((tile_is_v(np) ? p_v : p_k) + (size_t)tile_row(np) * (DH * 2), KV_BYTES);
              np++;
              t_ok = now + KV_PACE;
              t_sched += KV_SCHED;
            }
          }
          if (++it > (1u << 24)) __trap();
        }
        lag.advance<KV_SLOTS>();
        if (np == n) {
          uint32_t now = globaltimer_lo();
          while ((int)(now - t_sched) < 0) { __nanosleep(20); now = globaltimer_lo(); }
          t_ok = now + KV_PACE;
          t_sched += KV_SCHED;
          np++;
        }
        if (elect_one()) {
          const uint32_t fb = bars + (BAR_KVFULL + kv.slot) * 8;
          mbar_expect_tx(fb, KV_BYTES);
          tma3d_hint(sb + OFF_KV + kv.slot * KV_BYTES, tile_is_v(n) ? &m_v : &m_k, 0, tile_row(n), 0, fb, pol);
        }
        kv.advance<KV_SLOTS>();
      }
      if (lane == 0) TW_DUMP(63, npf);
      const uint32_t need = ldg_acq(&g_epoch) * 16 + NROUND;
      const int jo = (lane & 3) < j ? (lane & 3) : ((lane + 1) & 3);
      mbar_wait(bars + BAR_OLOCAL * 8, 0);
      uint32_t todo = 7, it = 0;
      while (todo) {
        uint32_t f = need - 1;
        if (lane < 3) f = ldg_acq(flags + jo);
        const uint32_t got = __ballot_sync(0xffffffffu, (int)(f - need) >= 0) & todo;
        if (got >> lane & 1) {
          fence_async_global();
          const uint32_t fb = bars + (BAR_OREM + lane) * 8;
          mbar_expect_tx(fb, 2 * TILE_B);
          bulk_load(sb + (lane < 2 ? OFF_KV + lane * 2 * TILE_B : OFF_P),
                    g_oscratch + (size_t)((b * 2 + ((NROUND - 1) & 1)) * 4 + jo) * 2 * TILE_B, 2 * TILE_B, fb);
          PROF(182 + 2 * lane); PROF(183 + 2 * lane);
        }
        __syncwarp();
        todo &= ~got;
        if (++it > (1u << 22)) __trap();
      }
    } else if (warp == 1) {
      Ring w{0, 1};
      const int cb = (j >> 1) * 5 + (j & 1) * 2;
      uint32_t base = 0;
#pragma unroll 1
      for (int step = 0; step < NROUND + 3; step++) {
        if (step >= 3) {
          const bool last = step == NROUND + 2;
#pragma unroll 1
          for (int kc = 0; kc < 8; kc++) {
            const int q = kc >> 1;
            const int hh = 4 * (step - 3) + (!last ? q : q == 0 ? j : q - 1 < j ? q - 1 : q);
            mbar_wait(bars + (BAR_WEMPTY + w.slot) * 8, w.phase);
            if (elect_one()) {
              const uint32_t fb = bars + (BAR_WFULL + w.slot) * 8;
              if (step == PSTEP) PROF(160 + kc);
              mbar_expect_tx(fb, last ? 24576 : 24576 + TILE_B);
              tma3d_mc(sb + OFF_W + w.slot * W_BYTES + rank * 12288, &m_wo, 0,
                       hh * DH + (kc & 1) * 64 + rank * 32, cb, fb, (uint16_t)3);
              if (step == NROUND + 1 && kc == W_SLOTS - 1)
                post4(post + 4, base + step - 3);
            }
            w.advance<W_SLOTS>();
          }
        }
        if (step < NROUND) {
#pragma unroll 1
          for (int kc = 0; kc < Q_STAGES; kc++) {
            mbar_wait(bars + (BAR_WEMPTY + w.slot) * 8, w.phase);
            if (elect_one()) {
              const uint32_t fb = bars + (BAR_WFULL + w.slot) * 8;
              if (step == PSTEP) PROF(150 + kc);
              mbar_expect_tx(fb, 20480 + TILE_B + 3072);
              tma3d_mc(sb + OFF_W + w.slot * W_BYTES + rank * 12288, &m_wq, 0, kc * 64 + rank * 32, (4 * step + j) * 2, fb, (uint16_t)3);
              tma3d_mc(sb + OFF_W + w.slot * W_BYTES + W_XA + rank * 2048, &m_wq2, 0, 512 + kc * 16, (4 * step + j) * 2 + rank, fb, (uint16_t)3);
              if (step >= 3 && kc == W_SLOTS - 1)
                post4(post + 4, base + step - 2);
            }
            w.advance<W_SLOTS>();
          }
          if (step == 1) base = ldg_acq(&g_epoch) * 16;
        }
      }
    } else if (warp == 2) {
      Ring w{0, 1};
#pragma unroll 1
      for (int step = 0; step < NROUND + 2; step++) {
        if (step >= 3) {
          smem_wait_ge(sb + OFF_CNT, step - 2);
#pragma unroll 1
          for (int kc = 0; kc < 8; kc++) {
            mbar_wait(bars + (BAR_WEMPTY + w.slot) * 8, w.phase);
            if (step == PSTEP && lane == 0) PROF(180 + kc);
            if (elect_one())
              bulk_load(sb + OFF_W + w.slot * W_BYTES + W_BOFF,
                        g_oscratch + ((size_t)(b * 2 + ((step - 3) & 1)) * 8 + kc) * TILE_B, TILE_B, bars + (BAR_WFULL + w.slot) * 8);
            w.advance<W_SLOTS>();
          }
        }
        if (step < NROUND) {
#pragma unroll 1
          for (int kc = 0; kc < Q_STAGES; kc++) {
            mbar_wait(bars + (BAR_WEMPTY + w.slot) * 8, w.phase);
            if (elect_one()) {
              tma5d_x(sb + OFF_W + w.slot * W_BYTES + W_BOFF, &m_x, kc * 64, b * 3, bars + (BAR_WFULL + w.slot) * 8);
              tma5d_x(sb + OFF_W + w.slot * W_BYTES + W_XB, &m_x2, 512 + kc * 16, b * 3, bars + (BAR_WFULL + w.slot) * 8);
            }
            w.advance<W_SLOTS>();
          }
        }
      }
    } else {
      const uint32_t base = ldg_acq(&g_epoch) * 16;
      auto wait4 = [&](const unsigned int* fp, uint32_t need) {
        uint32_t it = 0;
        while (true) {
          uint32_t f = need;
          if (lane < 4) f = ldg_acq(fp + lane);
          if (__all_sync(0xffffffffu, (int)(f - need) >= 0)) break;
          if (++it > (1u << 22)) __trap();
          __nanosleep(POLL_NS);
        }
      };
      mbar_wait(bars + (BAR_WFULL + W_SLOTS - 1) * 8, 0);
      if (elect_one()) {
        if (b < 20) tma3d_prefetch(&m_wq, 0, b * 32, (4 + j) * 2);
        prefetch_map(&m_wo);
        prefetch_map(&m_out);
        prefetch_map(&m_out16);
      }
      mbar_wait(bars + BAR_QFULL * 8, 0);
#pragma unroll 1
      for (int r = 0; r < NROUND; r++) {
        if (elect_one()) {
          if (b < 20 && r + 2 < NROUND) tma3d_prefetch(&m_wq, 0, b * 32, (4 * (r + 2) + j) * 2);
          l2_prefetch(p_wo + (size_t)r * (512 * DM * 2) + blockIdx.x * 5120, 5120);
        }
        if (r >= 2) wait4(flags + 4, base + r - 1);
        if (lane == 0) mbar_arrive(bars + BAR_OFREE * 8);
        mbar_wait(bars + BAR_OFULL * 8, r & 1);
        if (lane == 0) {
          if (r == NROUND - 1) { PROF(82); PROF(83); }
          asm volatile("fence.acq_rel.gpu;" ::: "memory");
          if (r == NROUND - 1) PROF(84);
          post4(post, base + r + 1);
          PROF(96 + r);
        }
        __syncwarp();
        if (r < NROUND - 1) {
          wait4(flags, base + r + 1);
          fence_async_global();
          __syncwarp();
          if (lane == 0) sts_rel(sb + OFF_CNT, r + 1);
        }
      }
    }
    cluster_arrive_relaxed();
    cluster_wait();
    if (threadIdx.x == 256) {
      unsigned int d = atomicAdd(&g_done, 1u);
      if (d == NCTA - 1) { g_done = 0; atomicAdd(&g_epoch, 1u); }
    }
  }
}

typedef CUresult (*PFN_encodeTiled)(CUtensorMap*, CUtensorMapDataType, cuuint32_t, void*, const cuuint64_t*, const cuuint64_t*,
                                    const cuuint32_t*, const cuuint32_t*, CUtensorMapInterleave, CUtensorMapSwizzle,
                                    CUtensorMapL2promotion, CUtensorMapFloatOOBfill);

CUtensorMap make_map(PFN_encodeTiled enc, const void* ptr, int rank, const cuuint64_t* dims, const cuuint64_t* strides, const cuuint32_t* box,
                     CUtensorMapSwizzle sw = CU_TENSOR_MAP_SWIZZLE_128B) {
  CUtensorMap m;
  cuuint32_t es[5] = {1, 1, 1, 1, 1};
  enc(&m, CU_TENSOR_MAP_DATA_TYPE_BFLOAT16, rank, const_cast<void*>(ptr), dims, strides, box, es, CU_TENSOR_MAP_INTERLEAVE_NONE,
      sw, CU_TENSOR_MAP_L2_PROMOTION_NONE, CU_TENSOR_MAP_FLOAT_OOB_FILL_NONE);
  return m;
}

}

extern "C" void kernel_launch(void* const* d_in, const int* in_sizes, int n_in, void* d_out, int out_size) {
  (void)in_sizes; (void)n_in; (void)out_size;
  void* fn = nullptr;
  cudaDriverEntryPointQueryResult qr;
  cudaGetDriverEntryPoint("cuTensorMapEncodeTiled", &fn, cudaEnableDefault, &qr);
  PFN_encodeTiled enc = (PFN_encodeTiled)fn;
  const void* x = d_in[0];
  const void* k = d_in[1];
  const void* v = d_in[2];
  const void* wq = d_in[3];
  const void* wo = d_in[4];
  CUtensorMap m_k, m_v, m_wq, m_wo, m_x, m_out, m_wq2, m_x2, m_out16;
  {
    cuuint64_t dims[3] = {64, (cuuint64_t)NB * NH * SK, 2}, str[2] = {DH * 2, 128};
    cuuint32_t box[3] = {64, 64, 2};
    m_k = make_map(enc, k, 3, dims, str, box);
    m_v = make_map(enc, v, 3, dims, str, box);
  }
  {
    cuuint64_t dims[3] = {64, DM, NH * DH / 64}, str[2] = {NH * DH * 2, 128};
    cuuint32_t box[3] = {64, 32, 2};
    m_wq = make_map(enc, wq, 3, dims, str, box);
    cuuint32_t box2[3] = {64, 16, 1};
    m_wq2 = make_map(enc, wq, 3, dims, str, box2);
  }
  {
    cuuint64_t dims[3] = {64, NH * DH, DM / 64}, str[2] = {DM * 2, 128};
    cuuint32_t box[3] = {64, 32, 3};
    m_wo = make_map(enc, wo, 3, dims, str, box);
  }
  {
    cuuint64_t dimx[5] = {DM, 2, 4, 4, NB * 3}, strx[4] = {DM * 2, 8 * DM * 2, 2 * DM * 2, 32 * DM * 2};
    cuuint32_t box[5] = {64, 2, 4, 4, 3}, box2[5] = {16, 2, 4, 4, 3};
    m_x = make_map(enc, x, 5, dimx, strx, box);
    m_x2 = make_map(enc, x, 5, dimx, strx, box2, CU_TENSOR_MAP_SWIZZLE_32B);
    cuuint64_t dims[2] = {DM, NB * SQ}, str[1] = {DM * 2};
    cuuint32_t boxo[2] = {64, SQ}, boxo16[2] = {64, 16};
    m_out = make_map(enc, d_out, 2, dims, str, boxo);
    m_out16 = make_map(enc, d_out, 2, dims, str, boxo16);
  }
  cudaFuncSetAttribute(gqa_block_kernel, cudaFuncAttributeMaxDynamicSharedMemorySize, SMEM_BYTES);
  gqa_block_kernel<<<NCTA, 384, SMEM_BYTES>>>(m_k, m_v, m_wq, m_wo, m_x, m_out, m_wq2, m_x2, m_out16, (const uint8_t*)x, (const uint8_t*)wo, (const uint8_t*)k, (const uint8_t*)v);
}
```
